```python
import torch

def _softmax(x, axis=-1):
    return torch.softmax(x, dim=axis)
def _gelu(x):
    return torch.nn.functional.gelu(x, approximate="tanh")
def _silu(x):
    return torch.nn.functional.silu(x)
def _sigmoid(x):
    return torch.sigmoid(x)
def _layernorm(x, axis=-1, eps=1e-5):
    m = x.mean(dim=axis, keepdim=True)
    v = x.var(dim=axis, keepdim=True, unbiased=False)
    return (x - m) / torch.sqrt(v + eps)
def _scatter_add(tgt, idx, src, axis=0):
    return tgt.clone().index_add_(axis, idx, src)
def _segment_sum(src, seg, n):
    out = torch.zeros((n,) + src.shape[1:], dtype=src.dtype)
    return out.index_add_(0, seg, src)
def _pad(x, pw):
    flat = tuple(v for pair in reversed(pw) for v in pair)
    return torch.nn.functional.pad(x, flat)

kernel_name = 'parallel_sum__softmax_full_mha__moe_arch_mod__prompt'

def setup_inputs():

    _w = (lambda a: (lambda t: t.to(torch.bfloat16) if t.is_floating_point() else t)(torch.as_tensor(a)))
    def _A_setup():
        B, S, D = 1, 2048, 640
        return {
            "x": _w((lambda *s: torch.randn(*s, dtype=torch.bfloat16) * 0.05)(B, S, D)),
            "wqkv": _w((lambda *s: torch.randn(*s, dtype=torch.bfloat16) * 0.2)(D, 3 * D)),
            "wo": _w((lambda *s: torch.randn(*s, dtype=torch.bfloat16) * 0.2)(D, D)),
        }
    _A_in = _A_setup()

    def _B_setup():
        B, S, D, F, C = 1, 2048, 640, 1728, 2
        return {
            "x": _w((lambda *s: torch.randn(*s, dtype=torch.bfloat16) * 0.05)(B, S, D)),
            "w_r": _w((lambda *s: torch.randn(*s, dtype=torch.bfloat16) * 0.8)(D)),
            "w_gate": _w((lambda *s: torch.randn(*s, dtype=torch.bfloat16) * 0.2)(D, F)),
            "w_up": _w((lambda *s: torch.randn(*s, dtype=torch.bfloat16) * 0.2)(D, F)),
            "w_down": _w((lambda *s: torch.randn(*s, dtype=torch.bfloat16) * 0.2)(F, D)),
        }
    _B_in = _B_setup()

    return {
        "A_x": _A_in["x"],
        "A_wqkv": _A_in["wqkv"],
        "A_wo": _A_in["wo"],
        "B_x": _B_in["x"],
        "B_w_r": _B_in["w_r"],
        "B_w_gate": _B_in["w_gate"],
        "B_w_up": _B_in["w_up"],
        "B_w_down": _B_in["w_down"],
    }

def reference(A_x, A_wqkv, A_wo, B_x, B_w_r, B_w_gate, B_w_up, B_w_down):
    def _A_ref(x, wqkv, wo):
        B, S, D = x.shape
        H = 32; Dh = D // H
        qkv = (lambda x, *d: x.permute(*d))((x @ wqkv).reshape(B, S, 3, H, Dh), 2, 0, 3, 1, 4)
        q, k, v = qkv[0], qkv[1], qkv[2]
        scale = Dh ** -0.5
        scores = torch.einsum("bhqd,bhkd->bhqk", q, k) * scale
        p = _softmax(scores, axis=-1)
        o = torch.einsum("bhqk,bhkd->bhqd", p, v)
        return (lambda x, *d: x.permute(*d))(o, 0, 2, 1, 3).reshape(B, S, D) @ wo

    def _B_ref(x, w_r, w_gate, w_up, w_down):
        B, S, D = x.shape
        C = 2
        r = x @ w_r
        idx = torch.argsort(-r, axis=-1)[:, :C]
        idx_e = (lambda x, n, axis: torch.repeat_interleave(x, n, dim=axis))(idx.reshape(B, C, 1), D, axis=2)
        x_sel = (lambda x, i, axis: torch.take_along_dim(x, i, dim=axis))(x, idx_e, axis=1)
        g = _silu(x_sel @ w_gate)
        u = x_sel @ w_up
        y = (g * u) @ w_down
        r_sel = _sigmoid((lambda x, i, axis: torch.take_along_dim(x, i, dim=axis))(r, idx, axis=1))
        y = y * r_sel.reshape(B, C, 1)
        b_off = (torch.arange(B) * S).reshape(B, 1)
        flat_idx = (idx + b_off).reshape(B * C)
        zero = (x * 0.0).reshape(B * S, D)
        upd = _scatter_add(zero, flat_idx, y.reshape(B * C, D), axis=0)
        return x + upd.reshape(B, S, D)

    x = A_x
    xn = _layernorm(x, axis=-1)
    return x + _A_ref(xn, A_wqkv, A_wo) + _B_ref(xn, B_w_r, B_w_gate, B_w_up, B_w_down)
```

```cpp
#include <cuda_runtime.h>
#include <cuda_bf16.h>
#include <cuda.h>
#include <stdint.h>

namespace {

constexpr int S_ = 2048, D_ = 640, H_ = 32, F_ = 1728;
constexpr int NM = 5;
constexpr int NP = 16 - NM;
constexpr float T_SHIFT = 96.f;

constexpr int QB0 = 2;
constexpr int STAGGER = 330;

__device__ __align__(1024) __nv_bfloat16 g_xn[S_ * D_];
__device__ __align__(1024) __nv_bfloat16 g_o[S_ * D_];
__device__ __align__(1024) uint8_t g_q[H_ * S_ * 48];
__device__ __align__(1024) uint8_t g_k[H_ * S_ * 48];
__device__ __align__(1024) uint8_t g_v[H_ * S_ * 48];
__device__ __align__(1024) uint8_t g_wo[4 * 204800];
__device__ float g_r[S_];
__device__ float g_y[4 * 2 * D_];
__device__ __align__(16) float g_part[4 * 2 * 2 * F_];
__device__ int g_idx[2];
__device__ float g_gate[2];
constexpr int C_LN = 0, C_QKV = 16, C_O = 24, C_MOE = 56, C_AUX = 57, C_MOE1 = 58, C_UNSAFE = 59, C_EXIT = 60, C_NUM = 61;
__device__ unsigned g_sync[C_NUM * 32];

constexpr int GA = 16384, GB = 32768, GST = GA + GB;
constexpr int AK = 0, AV = 98304, AQ = 196608;
constexpr int WB = 0, WA = 204800;
constexpr int BAR = WA + 3 * 8192;
constexpr int B_GF = BAR, B_GE = B_GF + 32, B_AT = B_GE + 32, B_AQ = B_AT + 72, B_WB = B_AQ + 8, B_WF = B_WB + 32, B_WE = B_WF + 88;
constexpr int LNX = 4 * GST;
constexpr int S_CNT = B_WE + 16;
constexpr int SMEM_BYTES = S_CNT + 32 + 1024;

__host__ __device__ constexpr bool is_poly(int i) { return ((i + 1) * NP) / 16 != (i * NP) / 16; }
__host__ __device__ constexpr int grp_idx(int i) { int n = 0; for (int j = 0; j < i; j++) n += is_poly(j) == is_poly(i) ? 1 : 0; return n; }
__host__ __device__ constexpr int k_slot(int i) { return is_poly(i) ? NM + grp_idx(i) : grp_idx(i); }
__host__ __device__ constexpr uint32_t poly_mask() { uint32_t m = 0; for (int i = 0; i < 16; i++) m |= (is_poly(i) ? 1u : 0u) << i; return m; }
__host__ __device__ constexpr uint64_t slot_table() { uint64_t m = 0; for (int i = 0; i < 16; i++) m |= (uint64_t)k_slot(i) << (4 * i); return m; }

__device__ __forceinline__ uint32_t smem_u32(const void* p) { return (uint32_t)__cvta_generic_to_shared(p); }
__device__ __forceinline__ void mbar_init(uint32_t bar, uint32_t cnt) { asm volatile("mbarrier.init.shared::cta.b64 [%0], %1;" ::"r"(bar), "r"(cnt) : "memory"); }
__device__ __forceinline__ void mbar_expect(uint32_t bar, uint32_t bytes) {
    asm volatile("mbarrier.arrive.expect_tx.shared::cta.b64 _, [%0], %1;" ::"r"(bar), "r"(bytes) : "memory");
}
__device__ __forceinline__ void mbar_arrive(uint32_t bar) { asm volatile("mbarrier.arrive.shared::cta.b64 _, [%0];" ::"r"(bar) : "memory"); }
__device__ __forceinline__ void mbar_wait(uint32_t bar, uint32_t parity) {
    asm volatile("{\n.reg .pred p;\n.reg .u32 n;\nmov.u32 n, 0;\n"
                 "WAIT_%=:\nmbarrier.try_wait.parity.shared::cta.b64 p, [%0], %1;\n@p bra DONE_%=;\n"
                 "add.u32 n, n, 1;\nsetp.lt.u32 p, n, 4194304;\n@p bra WAIT_%=;\ntrap;\nDONE_%=:\n}\n" ::"r"(bar), "r"(parity) : "memory");
}
__device__ __forceinline__ void signal(int c) {
    asm volatile("red.release.gpu.global.add.u32 [%0], 1;" ::"l"(g_sync + c * 32) : "memory");
}
__device__ __forceinline__ void await(int c, unsigned target) {
    unsigned v;
    for (int i = 0; i < (1 << 22); i++) {
        asm volatile("ld.acquire.gpu.global.u32 %0, [%1];" : "=r"(v) : "l"(g_sync + c * 32) : "memory");
        if (v >= target) return;
    }
    __trap();
}
__device__ __forceinline__ int tid_now() { int t; asm volatile("mov.u32 %0, %%tid.x;" : "=r"(t)); return t; }
__device__ __forceinline__ void fence_async_global() { asm volatile("fence.proxy.async.global;" ::: "memory"); }
__device__ __forceinline__ void fence_mbar_init() { asm volatile("fence.mbarrier_init.release.cluster;" ::: "memory"); }
__device__ __forceinline__ void fence_async_smem() { asm volatile("fence.proxy.async.shared::cta;" ::: "memory"); }
__device__ __forceinline__ void wg_bar(int wg) { asm volatile("barrier.sync %0, 128;" ::"r"(1 + wg) : "memory"); }
__device__ __forceinline__ void bulk_g2s(uint32_t dst, const void* src, uint32_t bytes, uint32_t bar) {
    asm volatile("cp.async.bulk.shared::cluster.global.mbarrier::complete_tx::bytes [%0], [%1], %2, [%3];" ::"r"(dst), "l"(src), "r"(bytes), "r"(bar) : "memory");
}
__device__ __forceinline__ void bulk_s2g(void* dst, uint32_t src, uint32_t bytes) {
    asm volatile("cp.async.bulk.global.shared::cta.bulk_group [%0], [%1], %2;" ::"l"(dst), "r"(src), "r"(bytes) : "memory");
}
__device__ __forceinline__ void bulk_commit() { asm volatile("cp.async.bulk.commit_group;" ::: "memory"); }
__device__ __forceinline__ void bulk_wait0() { asm volatile("cp.async.bulk.wait_group 0;" ::: "memory"); }
__device__ __forceinline__ void tma2d(uint32_t dst, const CUtensorMap* tm, int c0, int c1, uint32_t bar) {
    asm volatile("cp.async.bulk.tensor.2d.shared::cluster.global.mbarrier::complete_tx::bytes [%0], [%1, {%3, %4}], [%2];"
                 ::"r"(dst), "l"(tm), "r"(bar), "r"(c0), "r"(c1) : "memory");
}
__device__ __forceinline__ void cp_async16(uint32_t dst, const void* src) {
    asm volatile("cp.async.cg.shared.global [%0], [%1], 16;" ::"r"(dst), "l"(src) : "memory");
}
__device__ __forceinline__ void prefetch_tmap(const CUtensorMap* tm) { asm volatile("prefetch.tensormap [%0];" ::"l"(tm) : "memory"); }
__device__ __forceinline__ uint4 lds128(uint32_t a) {
    uint4 v;
    asm volatile("ld.shared.v4.b32 {%0,%1,%2,%3}, [%4];" : "=r"(v.x), "=r"(v.y), "=r"(v.z), "=r"(v.w) : "r"(a));
    return v;
}
__device__ __forceinline__ void stsm4(uint32_t a, uint32_t r0, uint32_t r1, uint32_t r2, uint32_t r3) {
    asm volatile("stmatrix.sync.aligned.m8n8.x4.shared.b16 [%0], {%1,%2,%3,%4};" ::"r"(a), "r"(r0), "r"(r1), "r"(r2), "r"(r3) : "memory");
}
__device__ __forceinline__ void wg_fence() { asm volatile("wgmma.fence.sync.aligned;" ::: "memory"); }
__device__ __forceinline__ void wg_commit() { asm volatile("wgmma.commit_group.sync.aligned;" ::: "memory"); }
template <int N> __device__ __forceinline__ void wg_wait() { asm volatile("wgmma.wait_group.sync.aligned %0;" ::"n"(N) : "memory"); }
template <int N> __device__ __forceinline__ void pin(float (&r)[N]) {
#pragma unroll
    for (int i = 0; i < N; i++) asm volatile("" : "+f"(r[i])::"memory");
}
template <int N> __device__ __forceinline__ void pin(uint32_t (&r)[N]) {
#pragma unroll
    for (int i = 0; i < N; i++) asm volatile("" : "+r"(r[i])::"memory");
}
__device__ __forceinline__ uint64_t make_desc(uint32_t addr, uint32_t lbo, uint32_t sbo, uint32_t swz) {
    return (uint64_t)((addr & 0x3FFFF) >> 4) | ((uint64_t)(lbo >> 4) << 16) | ((uint64_t)(sbo >> 4) << 32) | ((uint64_t)swz << 62);
}
__device__ __forceinline__ float bfr(float x) { return __bfloat162float(__float2bfloat16_rn(x)); }
__device__ __forceinline__ uint32_t pack_bf(float lo, float hi) {
    uint32_t r;
    asm("cvt.rn.bf16x2.f32 %0, %1, %2;" : "=r"(r) : "f"(hi), "f"(lo));
    return r;
}
__device__ __forceinline__ float bf_lo(uint32_t v) { return __uint_as_float(v << 16); }
__device__ __forceinline__ float bf_hi(uint32_t v) { return __uint_as_float(v & 0xFFFF0000u); }
__device__ __forceinline__ uint32_t mul_bf2(uint32_t a, uint32_t b) {
    uint32_t r;
    asm("mul.rn.bf16x2 %0, %1, %2;" : "=r"(r) : "r"(a), "r"(b));
    return r;
}

__device__ __forceinline__ uint32_t add_bf2(uint32_t a, uint32_t b) {
    uint32_t r;
    asm("add.rn.bf16x2 %0, %1, %2;" : "=r"(r) : "r"(a), "r"(b));
    return r;
}
__device__ __forceinline__ uint32_t sub_bf2(uint32_t a, uint32_t b) {
    uint32_t r;
    asm("sub.rn.bf16x2 %0, %1, %2;" : "=r"(r) : "r"(a), "r"(b));
    return r;
}
__device__ __forceinline__ uint32_t fma_bf2(uint32_t a, uint32_t b, uint32_t c) {
    uint32_t r;
    asm("fma.rn.bf16x2 %0, %1, %2, %3;" : "=r"(r) : "r"(a), "r"(b), "r"(c));
    return r;
}

template <int N, int TB> struct MmaRS;
template <int N, int TB> struct MmaSS;
template <> struct MmaRS<40, 0> {
    template <int M> static __device__ __forceinline__ void go(float (&d)[M], uint32_t a0, uint32_t a1, uint32_t a2, uint32_t a3, uint64_t b, int acc) {
        asm volatile("{\n.reg .pred p;\nsetp.ne.b32 p, %25, 0;\n"
            "wgmma.mma_async.sync.aligned.m64n40k16.f32.bf16.bf16 {%0,%1,%2,%3,%4,%5,%6,%7,%8,%9,%10,%11,%12,%13,%14,%15,%16,%17,%18,%19}, "
            "{%20,%21,%22,%23}, %24, p, 1, 1, 0;\n}\n"
        : "+f"(d[0]), "+f"(d[1]), "+f"(d[2]), "+f"(d[3]), "+f"(d[4]), "+f"(d[5]), "+f"(d[6]), "+f"(d[7]), "+f"(d[8]), "+f"(d[9]), "+f"(d[10]), "+f"(d[11]),
          "+f"(d[12]), "+f"(d[13]), "+f"(d[14]), "+f"(d[15]), "+f"(d[16]), "+f"(d[17]), "+f"(d[18]), "+f"(d[19])
        : "r"(a0), "r"(a1), "r"(a2), "r"(a3), "l"(b), "r"(acc));
    }
};
template <> struct MmaRS<88, 0> {
    template <int M> static __device__ __forceinline__ void go(float (&d)[M], uint32_t a0, uint32_t a1, uint32_t a2, uint32_t a3, uint64_t b, int acc) {
        asm volatile("{\n.reg .pred p;\nsetp.ne.b32 p, %49, 0;\n"
            "wgmma.mma_async.sync.aligned.m64n88k16.f32.bf16.bf16 {%0,%1,%2,%3,%4,%5,%6,%7,%8,%9,%10,%11,%12,%13,%14,%15,%16,%17,%18,%19,%20,%21,%22,%23,%24,%25,%26,%27,%28,%29,%30,%31,%32,%33,%34,%35,%36,%37,%38,%39,%40,%41,%42,%43}, "
            "{%44,%45,%46,%47}, %48, p, 1, 1, 0;\n}\n"
        : "+f"(d[0]), "+f"(d[1]), "+f"(d[2]), "+f"(d[3]), "+f"(d[4]), "+f"(d[5]), "+f"(d[6]), "+f"(d[7]), "+f"(d[8]), "+f"(d[9]), "+f"(d[10]), "+f"(d[11]),
          "+f"(d[12]), "+f"(d[13]), "+f"(d[14]), "+f"(d[15]), "+f"(d[16]), "+f"(d[17]), "+f"(d[18]), "+f"(d[19]), "+f"(d[20]), "+f"(d[21]), "+f"(d[22]),
          "+f"(d[23]), "+f"(d[24]), "+f"(d[25]), "+f"(d[26]), "+f"(d[27]), "+f"(d[28]), "+f"(d[29]), "+f"(d[30]), "+f"(d[31]), "+f"(d[32]), "+f"(d[33]),
          "+f"(d[34]), "+f"(d[35]), "+f"(d[36]), "+f"(d[37]), "+f"(d[38]), "+f"(d[39]), "+f"(d[40]), "+f"(d[41]), "+f"(d[42]), "+f"(d[43])
        : "r"(a0), "r"(a1), "r"(a2), "r"(a3), "l"(b), "r"(acc));
    }
};
template <> struct MmaRS<24, 1> {
    template <int M> static __device__ __forceinline__ void go(float (&d)[M], uint32_t a0, uint32_t a1, uint32_t a2, uint32_t a3, uint64_t b, int acc) {
        asm volatile("{\n.reg .pred p;\nsetp.ne.b32 p, %17, 0;\n"
            "wgmma.mma_async.sync.aligned.m64n24k16.f32.bf16.bf16 {%0,%1,%2,%3,%4,%5,%6,%7,%8,%9,%10,%11}, "
            "{%12,%13,%14,%15}, %16, p, 1, 1, 1;\n}\n"
        : "+f"(d[0]), "+f"(d[1]), "+f"(d[2]), "+f"(d[3]), "+f"(d[4]), "+f"(d[5]), "+f"(d[6]), "+f"(d[7]), "+f"(d[8]), "+f"(d[9]), "+f"(d[10]), "+f"(d[11])
        : "r"(a0), "r"(a1), "r"(a2), "r"(a3), "l"(b), "r"(acc));
    }
};
template <> struct MmaSS<240, 1> {
    static __device__ __forceinline__ void go(float (&d)[120], uint64_t a, uint64_t b, int acc) {
        asm volatile("{\n.reg .pred p;\nsetp.ne.b32 p, %122, 0;\n"
            "wgmma.mma_async.sync.aligned.m64n240k16.f32.bf16.bf16 {%0,%1,%2,%3,%4,%5,%6,%7,%8,%9,%10,%11,%12,%13,%14,%15,%16,%17,%18,%19,%20,%21,%22,%23,%24,%25,%26,%27,%28,%29,%30,%31,%32,%33,%34,%35,%36,%37,%38,%39,%40,%41,%42,%43,%44,%45,%46,%47,%48,%49,%50,%51,%52,%53,%54,%55,%56,%57,%58,%59,%60,%61,%62,%63,%64,%65,%66,%67,%68,%69,%70,%71,%72,%73,%74,%75,%76,%77,%78,%79,%80,%81,%82,%83,%84,%85,%86,%87,%88,%89,%90,%91,%92,%93,%94,%95,%96,%97,%98,%99,%100,%101,%102,%103,%104,%105,%106,%107,%108,%109,%110,%111,%112,%113,%114,%115,%116,%117,%118,%119}, "
            "%120, %121, p, 1, 1, 0, 1;\n}\n"
        : "+f"(d[0]), "+f"(d[1]), "+f"(d[2]), "+f"(d[3]), "+f"(d[4]), "+f"(d[5]), "+f"(d[6]), "+f"(d[7]), "+f"(d[8]), "+f"(d[9]), "+f"(d[10]), "+f"(d[11]),
          "+f"(d[12]), "+f"(d[13]), "+f"(d[14]), "+f"(d[15]), "+f"(d[16]), "+f"(d[17]), "+f"(d[18]), "+f"(d[19]), "+f"(d[20]), "+f"(d[21]), "+f"(d[22]),
          "+f"(d[23]), "+f"(d[24]), "+f"(d[25]), "+f"(d[26]), "+f"(d[27]), "+f"(d[28]), "+f"(d[29]), "+f"(d[30]), "+f"(d[31]), "+f"(d[32]), "+f"(d[33]),
          "+f"(d[34]), "+f"(d[35]), "+f"(d[36]), "+f"(d[37]), "+f"(d[38]), "+f"(d[39]), "+f"(d[40]), "+f"(d[41]), "+f"(d[42]), "+f"(d[43]), "+f"(d[44]),
          "+f"(d[45]), "+f"(d[46]), "+f"(d[47]), "+f"(d[48]), "+f"(d[49]), "+f"(d[50]), "+f"(d[51]), "+f"(d[52]), "+f"(d[53]), "+f"(d[54]), "+f"(d[55]),
          "+f"(d[56]), "+f"(d[57]), "+f"(d[58]), "+f"(d[59]), "+f"(d[60]), "+f"(d[61]), "+f"(d[62]), "+f"(d[63]), "+f"(d[64]), "+f"(d[65]), "+f"(d[66]),
          "+f"(d[67]), "+f"(d[68]), "+f"(d[69]), "+f"(d[70]), "+f"(d[71]), "+f"(d[72]), "+f"(d[73]), "+f"(d[74]), "+f"(d[75]), "+f"(d[76]), "+f"(d[77]),
          "+f"(d[78]), "+f"(d[79]), "+f"(d[80]), "+f"(d[81]), "+f"(d[82]), "+f"(d[83]), "+f"(d[84]), "+f"(d[85]), "+f"(d[86]), "+f"(d[87]), "+f"(d[88]),
          "+f"(d[89]), "+f"(d[90]), "+f"(d[91]), "+f"(d[92]), "+f"(d[93]), "+f"(d[94]), "+f"(d[95]), "+f"(d[96]), "+f"(d[97]), "+f"(d[98]), "+f"(d[99]),
          "+f"(d[100]), "+f"(d[101]), "+f"(d[102]), "+f"(d[103]), "+f"(d[104]), "+f"(d[105]), "+f"(d[106]), "+f"(d[107]), "+f"(d[108]), "+f"(d[109]),
          "+f"(d[110]), "+f"(d[111]), "+f"(d[112]), "+f"(d[113]), "+f"(d[114]), "+f"(d[115]), "+f"(d[116]), "+f"(d[117]), "+f"(d[118]), "+f"(d[119])
        : "l"(a), "l"(b), "r"(acc));
    }
};
template <> struct MmaSS<80, 1> {
    static __device__ __forceinline__ void go(float (&d)[40], uint64_t a, uint64_t b, int acc) {
        asm volatile("{\n.reg .pred p;\nsetp.ne.b32 p, %42, 0;\n"
            "wgmma.mma_async.sync.aligned.m64n80k16.f32.bf16.bf16 {%0,%1,%2,%3,%4,%5,%6,%7,%8,%9,%10,%11,%12,%13,%14,%15,%16,%17,%18,%19,%20,%21,%22,%23,%24,%25,%26,%27,%28,%29,%30,%31,%32,%33,%34,%35,%36,%37,%38,%39}, "
            "%40, %41, p, 1, 1, 0, 1;\n}\n"
        : "+f"(d[0]), "+f"(d[1]), "+f"(d[2]), "+f"(d[3]), "+f"(d[4]), "+f"(d[5]), "+f"(d[6]), "+f"(d[7]), "+f"(d[8]), "+f"(d[9]), "+f"(d[10]), "+f"(d[11]),
          "+f"(d[12]), "+f"(d[13]), "+f"(d[14]), "+f"(d[15]), "+f"(d[16]), "+f"(d[17]), "+f"(d[18]), "+f"(d[19]), "+f"(d[20]), "+f"(d[21]), "+f"(d[22]),
          "+f"(d[23]), "+f"(d[24]), "+f"(d[25]), "+f"(d[26]), "+f"(d[27]), "+f"(d[28]), "+f"(d[29]), "+f"(d[30]), "+f"(d[31]), "+f"(d[32]), "+f"(d[33]),
          "+f"(d[34]), "+f"(d[35]), "+f"(d[36]), "+f"(d[37]), "+f"(d[38]), "+f"(d[39])
        : "l"(a), "l"(b), "r"(acc));
    }
};


__device__ __forceinline__ float half_sum(float v) {
#pragma unroll
    for (int o = 8; o; o >>= 1) v += __shfl_xor_sync(0xffffffffu, v, o);
    return v;
}
__device__ __forceinline__ void ln_phase(uint32_t sb, int row, int l16) {
    const uint32_t xa = sb + LNX + (threadIdx.x >> 4) * 1280 + l16 * 16;
    const float pilot = bf_lo(lds128(xa - l16 * 16).x);
    float s = 0, q = 0;
#pragma unroll 1
    for (int i = 0; i < 5; i++) {
        const uint4 v = lds128(xa + 256 * i);
        const uint32_t e[4] = {v.x, v.y, v.z, v.w};
#pragma unroll
        for (int j = 0; j < 4; j++) {
            const float a = bf_lo(e[j]) - pilot, b = bf_hi(e[j]) - pilot;
            s += a + b; q = fmaf(a, a, fmaf(b, b, q));
        }
    }
    const float ms = half_sum(s) * (1.f / D_);
    const float var = fmaxf(half_sum(q) * (1.f / D_) - ms * ms, 0.f);
    const uint32_t mb = pack_bf(pilot + ms, pilot + ms);
    const float sd = bfr(sqrtf(bfr(bfr(var) + 1e-5f)));
    const float rc = 1.f / sd;
#pragma unroll 1
    for (int i = 0; i < 5; i++) {
        const uint4 v = lds128(xa + 256 * i);
        const uint32_t e[4] = {v.x, v.y, v.z, v.w};
        uint32_t o[4];
#pragma unroll
        for (int j = 0; j < 4; j++) {
            const uint32_t d = sub_bf2(e[j], mb);
            o[j] = pack_bf(bf_lo(d) * rc, bf_hi(d) * rc);
        }
        asm volatile("st.shared.v4.b32 [%0], {%1,%2,%3,%4};" ::"r"(xa + 256 * i), "r"(o[0]), "r"(o[1]), "r"(o[2]), "r"(o[3]) : "memory");
    }
    fence_async_smem();
}
__device__ __forceinline__ void ln_score(uint32_t sb, int row, int l16) {
    const uint32_t xa = sb + LNX + (threadIdx.x >> 4) * 1280 + l16 * 16, wa = sb + LNX + 16 * 1280 + l16 * 16;
    float dot = 0;
#pragma unroll 1
    for (int i = 0; i < 5; i++) {
        const uint4 v = lds128(xa + 256 * i), w = lds128(wa + 256 * i);
        const uint32_t e[4] = {v.x, v.y, v.z, v.w}, f[4] = {w.x, w.y, w.z, w.w};
#pragma unroll
        for (int j = 0; j < 4; j++) dot = fmaf(bf_lo(e[j]), bf_lo(f[j]), fmaf(bf_hi(e[j]), bf_hi(f[j]), dot));
    }
    dot = half_sum(dot);
    if (l16 == 0) g_r[row] = bfr(dot);
}

constexpr uint32_t BF_ONE = 0x3F80, BF_TINY = 0x1C00;

__device__ __forceinline__ uint32_t k_row_off(int tl) { return (uint32_t)((slot_table() >> (4 * (tl >> 3))) & 15) * 128 + (tl & 7) * 16; }
__device__ __forceinline__ uint32_t v_row_off(int tl) { return (tl >> 3) * 384 + (tl & 7) * 16; }

template <int M>
__device__ __forceinline__ void qkv_store_pair(const float (&acc)[120], uint32_t stg, int ty, uint32_t stK, uint32_t stV, uint32_t mxK, uint32_t mxV,
                                               uint32_t mdK, uint32_t ks0, uint32_t ks1, uint32_t& amax) {
    uint32_t v[10];
#pragma unroll
    for (int i = 0; i < 10; i++) v[i] = pack_bf(acc[20 * M + 2 * i], acc[20 * M + 2 * i + 1]);
    if (ty == 0) {
#pragma unroll
        for (int i = 0; i < 10; i++) v[i] = fma_bf2(v[i], 0x3EA53EA5u, mul_bf2(v[i], 0x39AD39ADu));
    } else if (ty == 1) {
#pragma unroll
        for (int i = 0; i < 10; i++) {
            asm("max.xorsign.abs.bf16x2 %0, %0, %1;" : "+r"(amax) : "r"(v[i]));
            v[i] = mul_bf2(v[i], (i & 1) ? ks1 : ks0);
        }
    }
    const uint32_t base = stg + 2 * M * 6144, st = ty == 1 ? stK : stV, mx = ty == 1 ? mxK : mxV, md = ty == 1 ? mdK : 384;
    stsm4(base + st, v[0], v[1], v[2], v[3]);
    stsm4(base + 6144 + st, v[6], v[7], v[8], v[9]);
    asm volatile("st.shared.b32 [%0], %1;" ::"r"(base + mx), "r"(v[4]) : "memory");
    asm volatile("st.shared.b32 [%0], %1;" ::"r"(base + mx + md), "r"(v[5]) : "memory");
}

__device__ __forceinline__ void qkv_epilogue(const float (&acc)[120], uint32_t stg, int mb, int nb) {
    const int tid = threadIdx.x, lane = tid & 31, c = lane & 3;
    const int slab = (tid >> 5) * 16, tl = slab + (lane >> 2);
    const int tm = slab + (lane & 15);
    const uint32_t stK = k_row_off((tm & ~15) + ((lane >> 3) & 1) * 8 + (lane & 7)) + (lane >> 4) * 2048;
    const uint32_t stV = v_row_off((tm & ~15) + ((lane >> 3) & 1) * 8 + (lane & 7)) + (lane >> 4) * 128;
    const uint32_t mxK = (c >> 1) * 6144 + k_row_off(tl) + 2 * 2048 + 4 * (c & 1), mxV = (c >> 1) * 6144 + v_row_off(tl) + 2 * 128 + 4 * (c & 1);
    const uint32_t mdK = k_row_off(tl + 8) - k_row_off(tl);
    const uint32_t TINY2 = BF_TINY | (BF_TINY << 16), ONE2 = BF_ONE | (BF_ONE << 16);
    const uint32_t ks0 = ((poly_mask() >> (tl >> 3)) & 1) ? TINY2 : ONE2, ks1 = ((poly_mask() >> ((tl >> 3) + 1)) & 1) ? TINY2 : ONE2;
    uint32_t amax = 0;
    qkv_store_pair<0>(acc, stg, (12 * nb + 0) >> 5, stK, stV, mxK, mxV, mdK, ks0, ks1, amax);
    qkv_store_pair<1>(acc, stg, (12 * nb + 2) >> 5, stK, stV, mxK, mxV, mdK, ks0, ks1, amax);
    qkv_store_pair<2>(acc, stg, (12 * nb + 4) >> 5, stK, stV, mxK, mxV, mdK, ks0, ks1, amax);
    qkv_store_pair<3>(acc, stg, (12 * nb + 6) >> 5, stK, stV, mxK, mxV, mdK, ks0, ks1, amax);
    qkv_store_pair<4>(acc, stg, (12 * nb + 8) >> 5, stK, stV, mxK, mxV, mdK, ks0, ks1, amax);
    qkv_store_pair<5>(acc, stg, (12 * nb + 10) >> 5, stK, stV, mxK, mxV, mdK, ks0, ks1, amax);
    if ((amax & 0x7FFF) > 0x5380 || ((amax >> 16) & 0x7FFF) > 0x5380) atomicExch(&g_sync[C_UNSAFE * 32], 1u);
    {
        const int t = tid & 127;
        const bool p = (poly_mask() >> (t >> 3)) & 1;
        const uint32_t offK = 2 * 2048 + k_row_off(t) + 8, offV = 2 * 128 + v_row_off(t) + 8;
#pragma unroll 1
        for (int hs = tid >> 7; hs < 12; hs += 2) {
            const int ty = (12 * nb + hs) >> 5;
            const uint32_t lo = ty == 0 ? 0u : (ty == 1 ? (p ? TINY2 : ONE2) : BF_ONE), hi = (ty == 1 && p) ? BF_TINY : 0u;
            asm volatile("st.shared.v2.b32 [%0], {%1, %2};" ::"r"(stg + hs * 6144 + (ty == 1 ? offK : offV)), "r"(lo), "r"(hi) : "memory");
        }
    }
    fence_async_smem();
    __syncthreads();
    if ((tid & 31) == 0) {
        for (int hs = tid >> 5; hs < 12; hs += 8) {
            const int gs = 12 * nb + hs, ty = gs >> 5, head = gs & 31;
            uint8_t* dst = (ty == 0 ? g_q : (ty == 1 ? g_k : g_v)) + (size_t)head * (S_ * 48) + mb * 6144;
            bulk_s2g(dst, stg + hs * 6144, 6144);
        }
        bulk_commit();
        bulk_wait0();
        fence_async_global();
        signal(C_QKV + nb);
    }
}

__device__ __forceinline__ void qkv_issue_b(uint32_t sb, const CUtensorMap* tmB, int kb, int nb) {
    const int s = kb & 3;
    mbar_expect(sb + B_GF + 8 * s, GST);
#pragma unroll
    for (int i = 0; i < 4; i++) tma2d(sb + s * GST + GA + i * 8192, tmB, nb * 240 + i * 64, kb * 64, sb + B_GF + 8 * s);
}
__device__ __forceinline__ void qkv_issue_a(uint32_t sb, const CUtensorMap* tmA, int kb, int mb) {
    tma2d(sb + (kb & 3) * GST, tmA, kb * 64, mb * 128, sb + B_GF + 8 * (kb & 3));
}

__device__ __forceinline__ void qkv_phase(uint32_t sb, const CUtensorMap* tmA, const CUtensorMap* tmB, int mb, int nb) {
    const int tid = threadIdx.x, wg = tid >> 7;
    float acc[120];
#pragma unroll
    for (int i = 0; i < 120; i++) acc[i] = 0.f;
    pin(acc);
    for (int kb = 0; kb < 10; kb++) {
        const int s = kb & 3;
        mbar_wait(sb + B_GF + 8 * s, (kb >> 2) & 1);
        const uint64_t da = make_desc(sb + s * GST + wg * 8192, 16, 1024, 1);
        const uint64_t db = make_desc(sb + s * GST + GA, 8192, 1024, 1);
        wg_fence();
#pragma unroll
        for (int k = 0; k < 4; k++) MmaSS<240, 1>::go(acc, da + 2 * k, db + 128 * k, 1);
        wg_commit();
        wg_wait<1>();
        if (kb >= 1) {
            const int ps = (kb - 1) & 3;
            if ((tid & 127) == 0) mbar_arrive(sb + B_GE + 8 * ps);
            if (tid == 0 && kb + 3 < 10) {
                mbar_wait(sb + B_GE + 8 * ps, ((kb - 1) >> 2) & 1);
                qkv_issue_b(sb, tmB, kb + 3, nb);
                qkv_issue_a(sb, tmA, kb + 3, mb);
            }
        }
    }
    wg_wait<0>();
    pin(acc);
    __syncthreads();
    qkv_epilogue(acc, sb, mb, nb);
}

constexpr uint32_t BF2_2M71 = BF_TINY | (BF_TINY << 16);
constexpr uint64_t TILE16 = 6144 >> 4;
constexpr float UP71 = 2.3611832414348226e+21f;

__device__ __forceinline__ float ex2(float x) { float r; asm("ex2.approx.ftz.f32 %0, %1;" : "=f"(r) : "f"(x)); return r; }
__device__ __forceinline__ uint32_t exp_mufu(float a, float b) { return pack_bf(ex2(a), ex2(b)); }
__device__ __forceinline__ uint32_t exp_alu(float a, float b, uint32_t half2) {
    uint32_t L, G, E, q;
    asm("cvt.pack.sat.s16.s32 %0, %1, %2;" : "=r"(L) : "r"(__float_as_int(b)), "r"(__float_as_int(a)));
    asm("lop3.b32 %0, %1, 0x007F007F, %2, 0xEA;" : "=r"(G) : "r"(L), "r"(half2));
    asm("and.b32 %0, %1, 0xFF80FF80;" : "=r"(E) : "r"(L));
    asm("fma.rn.bf16x2 %0, %1, %2, %3;" : "=r"(q) : "r"(G), "r"(L), "r"(E));
    return q;
}

constexpr uint64_t KSTEP2 = (uint64_t)(4096 >> 4) - ((uint64_t)(2048 >> 4) << 16);
__device__ __forceinline__ void issue_qk(float (&sm)[NM * 4], float (&sp)[NP * 4], const uint32_t (&q)[8], const uint32_t (&qp)[8], uint64_t kd) {
    MmaRS<NM * 8, 0>::go(sm, q[0], q[1], q[2], q[3], kd, 0);
    MmaRS<NP * 8, 0>::go(sp, qp[0], qp[1], qp[2], qp[3], kd + NM * 8, 0);
    MmaRS<NM * 8, 0>::go(sm, q[4], q[5], q[6], q[7], kd + KSTEP2, 1);
    MmaRS<NP * 8, 0>::go(sp, qp[4], qp[5], qp[6], qp[7], kd + (KSTEP2 + NM * 8), 1);
}
constexpr int PK = 4, PB = 2, NG = 8 / PK, PREGS = 4 * PK * PB;
template <int I, int B> __device__ __forceinline__ void exp_group(const float (&cm)[NM * 4], const float (&cp)[NP * 4], uint32_t (&p)[PREGS], uint32_t half2) {
    constexpr int ix = grp_idx(I);
    if constexpr (is_poly(I)) {
        p[B] = exp_alu(cp[4 * ix], cp[4 * ix + 1], half2);
        p[B + 1] = exp_alu(cp[4 * ix + 2], cp[4 * ix + 3], half2);
    } else {
        p[B] = exp_mufu(cm[4 * ix], cm[4 * ix + 1]);
        p[B + 1] = exp_mufu(cm[4 * ix + 2], cm[4 * ix + 3]);
    }
}
template <int I, int IE, int B> __device__ __forceinline__ void exp_groups(const float (&cm)[NM * 4], const float (&cp)[NP * 4], uint32_t (&p)[PREGS], uint32_t half2) {
    if constexpr (I < IE) { exp_group<I, B>(cm, cp, p, half2); exp_groups<I + 1, IE, B + 2>(cm, cp, p, half2); }
}
template <int G, int BUF> __device__ __forceinline__ void exp_pv(const float (&cm)[NM * 4], const float (&cp)[NP * 4], uint32_t (&p)[PREGS], float (&o)[12],
                                                                 uint32_t half2, uint64_t vd, int acc0) {
    constexpr int B = BUF * 4 * PK;
    exp_groups<2 * PK * G, 2 * PK * (G + 1), B>(cm, cp, p, half2);
    wg_fence();
#pragma unroll
    for (int k = 0; k < PK; k++)
        MmaRS<24, 1>::go(o, p[B + 4 * k], p[B + 4 * k + 1], p[B + 4 * k + 2], p[B + 4 * k + 3], vd + (PK * G + k) * 48, (G == 0 && k == 0) ? acc0 : 1);
    wg_commit();
}
template <int G, int PAR> __device__ __forceinline__ void exp_pv_all(const float (&cm)[NM * 4], const float (&cp)[NP * 4], uint32_t (&p)[PREGS], float (&o)[12],
                                                                     uint32_t half2, uint64_t vd, int acc0) {
    if constexpr (G < NG) {
        wg_wait<(PB - 1) + (G < PB ? 1 : 0)>();
        exp_pv<G, (G + PAR * NG) % PB>(cm, cp, p, o, half2, vd, acc0);
        exp_pv_all<G + 1, PAR>(cm, cp, p, o, half2, vd, acc0);
    }
}

__device__ __forceinline__ void load_q(uint32_t (&q)[8], uint32_t qaddr, uint32_t qzero) {
#pragma unroll
    for (int i = 0; i < 3; i++) {
        asm volatile("ld.shared.b32 %0, [%1];" : "=r"(q[i == 2 ? 4 : 2 * i]) : "r"(qaddr + 128 * i));
        asm volatile("ld.shared.b32 %0, [%1];" : "=r"(q[i == 2 ? 5 : 2 * i + 1]) : "r"(qaddr + 384 + 128 * i));
    }
    asm volatile("ld.shared.b32 %0, [%1];" : "=r"(q[6]) : "r"(qzero));
    asm volatile("ld.shared.b32 %0, [%1];" : "=r"(q[7]) : "r"(qzero + 4));
}
__device__ __forceinline__ uint32_t q_addr(uint32_t sb, int it) {
    const int tid = tid_now();
    return sb + AQ + (((tid >> 7) + 2 * it) * 8 + ((tid >> 5) & 3) * 2) * 384 + ((tid & 31) >> 2) * 16 + 4 * (tid & 3);
}
constexpr int QZERO = AQ + 256 + 8;
__device__ __forceinline__ void load_q_if(uint32_t (&q)[8], uint32_t (&qp)[8], uint32_t a, int on) {
    asm volatile("{\n.reg .pred p;\nsetp.ne.b32 p, %13, 0;\n"
                 "@p ld.shared.b32 %0, [%12];\n@p ld.shared.b32 %1, [%12 + 384];\n@p ld.shared.b32 %2, [%12 + 128];\n"
                 "@p ld.shared.b32 %3, [%12 + 512];\n@p ld.shared.b32 %4, [%12 + 256];\n@p ld.shared.b32 %5, [%12 + 640];\n"
                 "@p ld.shared.b32 %6, [%12];\n@p ld.shared.b32 %7, [%12 + 384];\n@p ld.shared.b32 %8, [%12 + 128];\n"
                 "@p ld.shared.b32 %9, [%12 + 512];\n@p ld.shared.b32 %10, [%12 + 256];\n@p ld.shared.b32 %11, [%12 + 640];\n}\n"
                 : "+r"(q[0]), "+r"(q[1]), "+r"(q[2]), "+r"(q[3]), "+r"(q[4]), "+r"(q[5]),
                   "+r"(qp[0]), "+r"(qp[1]), "+r"(qp[2]), "+r"(qp[3]), "+r"(qp[4]), "+r"(qp[5])
                 : "r"(a), "r"(on));
}

template <int PAR>
__device__ __forceinline__ void tile_step(float (&cm)[NM * 4], float (&cp)[NP * 4], float (&nm)[NM * 4], float (&np)[NP * 4], float (&o)[12],
                                          uint32_t (&p)[PREGS], const uint32_t (&q)[8], const uint32_t (&qp)[8], uint32_t half2, uint64_t kd, uint64_t vd,
                                          int acc0) {
    wg_fence();
    issue_qk(nm, np, q, qp, kd);
    wg_commit();
    exp_pv_all<0, PAR>(cm, cp, p, o, half2, vd, acc0);
    if constexpr (NG <= PB) wg_wait<NG>();
    pin(nm); pin(np);
}

__device__ __forceinline__ float quad_max(float v) {
    v = fmaxf(v, __shfl_xor_sync(0xffffffffu, v, 1));
    return fmaxf(v, __shfl_xor_sync(0xffffffffu, v, 2));
}
__device__ __forceinline__ void store_o(const float (&o)[12], float inv0, float inv1, int head, int row, int c) {
    const int odd = head & 1;
    __nv_bfloat16* d0 = g_o + (size_t)row * D_ + head * 20 + 2 * c + 4 * odd;
    __nv_bfloat16* d2 = d0 + 16 - 20 * odd;
    *reinterpret_cast<uint32_t*>(d0) = pack_bf(o[0] * inv0, o[1] * inv0);
    *reinterpret_cast<uint32_t*>(d0 + 8 * D_) = pack_bf(o[2] * inv1, o[3] * inv1);
    *reinterpret_cast<uint32_t*>(d0 + 8) = pack_bf(o[4] * inv0, o[5] * inv0);
    *reinterpret_cast<uint32_t*>(d0 + 8 * D_ + 8) = pack_bf(o[6] * inv1, o[7] * inv1);
    asm volatile("{\n.reg .pred p;\nsetp.lt.s32 p, %3, 2;\n@p st.global.b32 [%0], %1;\n@p st.global.b32 [%0 + 10240], %2;\n}\n"
                 ::"l"(d2), "r"(pack_bf(o[8] * inv0, o[9] * inv0)), "r"(pack_bf(o[10] * inv1, o[11] * inv1)), "r"(c) : "memory");
}

template <int I>
__device__ __forceinline__ void exact_groups(const float (&sm)[NM * 4], const float (&sp)[NP * 4], uint32_t (&p)[32], float up, float m0, float m1) {
    if constexpr (I < 16) {
        constexpr int ix = grp_idx(I);
        if constexpr (is_poly(I)) {
            p[2 * I] = exp_mufu(fmaf(sp[4 * ix], up, -m0), fmaf(sp[4 * ix + 1], up, -m0));
            p[2 * I + 1] = exp_mufu(fmaf(sp[4 * ix + 2], up, -m1), fmaf(sp[4 * ix + 3], up, -m1));
        } else {
            p[2 * I] = exp_mufu(sm[4 * ix] - m0, sm[4 * ix + 1] - m0);
            p[2 * I + 1] = exp_mufu(sm[4 * ix + 2] - m1, sm[4 * ix + 3] - m1);
        }
        exact_groups<I + 1>(sm, sp, p, up, m0, m1);
    }
}
__device__ __forceinline__ void attn_tile_exact(uint32_t qaddr, uint32_t qzero, uint64_t kd0, uint64_t vd0, float up, int head, int row, int c) {
    uint32_t q[8], p[32];
    float sm[NM * 4], sp[NP * 4], o[12];
    load_q(q, qaddr, qzero);
    float m0 = -INFINITY, m1 = -INFINITY;
#pragma unroll
    for (int i = 0; i < NM * 4; i++) sm[i] = 0;
#pragma unroll
    for (int i = 0; i < NP * 4; i++) sp[i] = 0;
#pragma unroll
    for (int i = 0; i < 12; i++) o[i] = 0;
#pragma unroll
    for (int i = 0; i < 32; i++) p[i] = 0;
    for (int pass = 0; pass < 2; pass++) {
#pragma unroll 1
        for (int t = 0; t < 16; t++) {
            pin(sm); pin(sp); pin(o); pin(q); pin(p);
            wg_fence();
            issue_qk(sm, sp, q, q, kd0 + t * TILE16);
            wg_commit();
            wg_wait<0>();
            pin(sm); pin(sp);
            if (pass == 0) {
#pragma unroll
                for (int i = 0; i < NM * 4; i++) { if (i & 2) m1 = fmaxf(m1, sm[i]); else m0 = fmaxf(m0, sm[i]); }
#pragma unroll
                for (int i = 0; i < NP * 4; i++) { if (i & 2) m1 = fmaxf(m1, sp[i] * up); else m0 = fmaxf(m0, sp[i] * up); }
            } else {
                exact_groups<0>(sm, sp, p, up, m0, m1);
                pin(p);
                wg_fence();
#pragma unroll
                for (int kk = 0; kk < 8; kk++)
                    MmaRS<24, 1>::go(o, p[4 * kk], p[4 * kk + 1], p[4 * kk + 2], p[4 * kk + 3], vd0 + t * TILE16 + kk * 48, 1);
                wg_commit();
                wg_wait<0>();
                pin(o);
            }
        }
        if (pass == 0) { m0 = quad_max(m0); m1 = quad_max(m1); }
    }
    const float l0 = __shfl_sync(0xffffffffu, o[8], 2, 4), l1 = __shfl_sync(0xffffffffu, o[10], 2, 4);
    store_o(o, 1.f / l0, 1.f / l1, head, row, c);
}

__device__ __forceinline__ void wo_issue_b(uint32_t sb, int cs, int ev) {
    const uint32_t lo = ev ? 6144 + 24576 * ev : 0, hi = 6144 + 24576 * (ev + 1);
    const uint32_t k1 = ev == 3 ? AV : hi, v1 = ev == 3 ? 184320 : AV + hi;
    const uint8_t* src = g_wo + cs * 204800;
    mbar_expect(sb + B_WB + 8 * ev, (k1 - lo) + (v1 - AV - lo));
    bulk_g2s(sb + WB + lo, src + lo, k1 - lo, sb + B_WB + 8 * ev);
    bulk_g2s(sb + WB + AV + lo, src + AV + lo, v1 - AV - lo, sb + B_WB + 8 * ev);
}
__device__ __forceinline__ void wo_release(uint32_t sb, int cs, int ev) {
    if ((tid_now() & 127) == 0) {
        uint32_t old;
        asm volatile("atom.relaxed.cta.shared.add.u32 %0, [%1], 1;" : "=r"(old) : "r"(sb + S_CNT + 4 * ev) : "memory");
        if (old == 1) wo_issue_b(sb, cs, ev);
    }
}
__device__ __forceinline__ void attn_issue_q(uint32_t sb, int head, int quarter) {
    mbar_expect(sb + B_AQ, 24576);
    bulk_g2s(sb + AQ, g_q + (size_t)head * (S_ * 48) + quarter * 24576, 24576, sb + B_AQ);
}
__device__ __forceinline__ void attn_issue_kv(uint32_t sb, int head, int g0, int g1) {
#pragma unroll 1
    for (int g = g0; g < g1; g++) {
        const int t = g ? 2 * g - 1 : 0;
        const uint32_t bytes = (g == 0 || g == 8) ? 6144 : 12288;
        mbar_expect(sb + B_AT + 8 * g, 2 * bytes);
        bulk_g2s(sb + AK + t * 6144, g_k + (size_t)head * (S_ * 48) + t * 6144, bytes, sb + B_AT + 8 * g);
        bulk_g2s(sb + AV + t * 6144, g_v + (size_t)head * (S_ * 48) + t * 6144, bytes, sb + B_AT + 8 * g);
    }
}

__device__ __forceinline__ uint32_t attn_offsets(const float (&am)[NM * 4], const float (&ap)[NP * 4], uint32_t (&q)[8], uint32_t (&qp)[8], int c) {
    float m0 = -INFINITY, m1 = -INFINITY, n0p = -INFINITY, n1p = -INFINITY;
#pragma unroll
    for (int i = 0; i < NM * 4; i += 4) { m0 = fmaxf(m0, fmaxf(am[i], am[i + 1])); m1 = fmaxf(m1, fmaxf(am[i + 2], am[i + 3])); }
#pragma unroll
    for (int i = 0; i < NP * 4; i += 4) { n0p = fmaxf(n0p, fmaxf(ap[i], ap[i + 1])); n1p = fmaxf(n1p, fmaxf(ap[i + 2], ap[i + 3])); }
    m0 = quad_max(fmaxf(m0, n0p * UP71)); m1 = quad_max(fmaxf(m1, n1p * UP71));
    uint32_t big = 0;
#pragma unroll
    for (int i = 0; i < 6; i++) asm("max.xorsign.abs.bf16x2 %0, %0, %1;" : "+r"(big) : "r"(q[i]));
    const uint32_t n0 = __bfloat16_as_ushort(__float2bfloat16_rn(-(m0 + T_SHIFT))), n1 = __bfloat16_as_ushort(__float2bfloat16_rn(-(m1 + T_SHIFT)));
    const uint32_t e0 = c == 2 ? (n0 | (0x42FEu << 16)) : (c == 3 ? 0x3C00u : q[4]);
    const uint32_t e1 = c == 2 ? (n1 | (0x42FEu << 16)) : (c == 3 ? 0x3C00u : q[5]);
#pragma unroll
    for (int i = 0; i < 8; i++) qp[i] = mul_bf2(i == 4 ? e0 : (i == 5 ? e1 : q[i]), BF2_2M71);
    q[4] = c == 2 ? (n0 | (0x3F16u << 16)) : q[4];
    q[5] = c == 2 ? (n1 | (0x3F16u << 16)) : q[5];
    pin(q); pin(qp);
    return __vmaxu2(big & 0x7FFF7FFFu, 0x53805380u) ^ 0x53805380u;
}

__device__ __forceinline__ uint32_t attn_finish(const float (&o)[12], int head, int quarter, int it) {
    const int tid = tid_now(), c = tid & 3, qt = (tid >> 7) + 2 * it;
    const int row = quarter * 512 + qt * 64 + ((tid >> 5) & 3) * 16 + ((tid & 31) >> 2);
    const float l0 = __shfl_sync(0xffffffffu, o[8], 2, 4), l1 = __shfl_sync(0xffffffffu, o[10], 2, 4);
    const uint32_t keep = c < 2 ? 0x7FFF7FFFu : 0u;
    uint32_t e = __vmaxu2(__vmaxu2(pack_bf(o[0], o[2]) & 0x7FFF7FFFu, pack_bf(o[1], o[3]) & 0x7FFF7FFFu),
                          __vmaxu2(pack_bf(o[4], o[6]) & 0x7FFF7FFFu, pack_bf(o[5], o[7]) & 0x7FFF7FFFu));
    e = __vmaxu2(e, __vmaxu2(pack_bf(o[8], o[10]) & keep, pack_bf(o[9], o[11]) & keep));
    e = __vmaxu2(e, __shfl_xor_sync(0xffffffffu, e, 1));
    e = __vmaxu2(e, __shfl_xor_sync(0xffffffffu, e, 2));
    float r0, r1;
    asm("rcp.approx.ftz.f32 %0, %1;" : "=f"(r0) : "f"(l0));
    asm("rcp.approx.ftz.f32 %0, %1;" : "=f"(r1) : "f"(l1));
    store_o(o, r0, r1, head, row, c);
    const uint32_t LO = (127u - 115u) << 7, HI = (127u + 120u) << 7;
    const uint32_t ll = pack_bf(l0, l1);
    const uint32_t mn = __vminu2(e, ll), mx = __vmaxu2(e, ll);
    return (__vminu2(mn, LO | (LO << 16)) ^ (LO | (LO << 16))) | (__vmaxu2(mx, (HI - 1) | ((HI - 1) << 16)) ^ ((HI - 1) | ((HI - 1) << 16)));
}

__device__ __forceinline__ void attn_phase(uint32_t sb, int head, int quarter, int cs,
                                           const __nv_bfloat16* __restrict__ wqkv, uint32_t& wpar) {
    __syncthreads();
    if ((threadIdx.x & 127) < 4) {
        const int j = threadIdx.x & 127;
        if (j < 3) await(C_QKV + (32 * j + head) / 12, 128); else await(C_AUX, 128);
    }
    __syncwarp();
    if ((threadIdx.x & 127) == 0) fence_async_global();
    if (threadIdx.x == 0) {
        attn_issue_kv(sb, head, 0, 1); attn_issue_q(sb, head, quarter); attn_issue_kv(sb, head, 1, 2);
        asm volatile("st.shared.u32 [%0], %1;" ::"r"(sb + S_CNT + 16), "r"(__ldcg(&g_sync[C_UNSAFE * 32])) : "memory");
        attn_issue_kv(sb, head, 2, 3);
    }
    if (threadIdx.x == 128) attn_issue_kv(sb, head, 3, 9);
    const uint64_t kd0 = make_desc(sb + AK, 2048, 128, 0), vd0 = make_desc(sb + AV, 384, 128, 0);
    const uint32_t half2 = 0x3F003F00u;
    uint32_t badmask;
    {
        float am[NM * 4], ap[NP * 4], bm[NM * 4], bp[NP * 4], o[12];
        uint32_t q[8], qp[8], p[PREGS];
#pragma unroll
        for (int i = 0; i < NM * 4; i++) { am[i] = 0; bm[i] = 0; }
#pragma unroll
        for (int i = 0; i < NP * 4; i++) { ap[i] = 0; bp[i] = 0; }
#pragma unroll
        for (int i = 0; i < 12; i++) o[i] = 0;
#pragma unroll
        for (int i = 0; i < PREGS; i++) p[i] = 0;
        mbar_wait(sb + B_AQ, 0);
        load_q(q, q_addr(sb, 0), sb + QZERO);
        mbar_wait(sb + B_AT, 0);
        badmask = 0;
        pin(am); pin(bm); pin(ap); pin(bp); pin(o); pin(q); pin(p);
        wg_fence();
        issue_qk(am, ap, q, q, kd0);
        wg_commit();
        wg_wait<0>();
        pin(am); pin(ap);
        uint32_t big = attn_offsets(am, ap, q, qp, tid_now() & 3);
        wg_fence();
        issue_qk(am, ap, q, qp, kd0);
        wg_commit();
        wg_wait<0>();
        pin(am); pin(ap);
#pragma unroll 1
        for (int it = 0; it < 4; it++) {
            const uint32_t qnext = q_addr(sb, (it + 1) & 3);
            if (it == 0 && threadIdx.x >= 128) { const long long t0 = clock64(); while (clock64() - t0 < STAGGER) {} }
#pragma unroll 1
            for (int tp = 0; tp < 8; tp++) {
                if (it == 0) mbar_wait(sb + B_AT + 8 * (tp + 1), 0);
                const uint32_t u = __shfl_sync(0xffffffffu, tp, 0);
                const uint64_t kd = kd0 + (2 * u + 1) * TILE16, vd = vd0 + 2 * u * TILE16;
                tile_step<0>(am, ap, bm, bp, o, p, q, qp, half2, kd, vd, u != 0);
                load_q_if(q, qp, qnext, u == 7);
                tile_step<1>(bm, bp, am, ap, o, p, q, qp, half2, u == 7 ? kd0 : kd + TILE16, vd + TILE16, 1);
                if (__builtin_expect(it == 3 && (tp & 1) == 0 && tp > 0, 0)) wo_release(sb, cs, (tp >> 1) - 1);
            }
            const uint32_t bignext = attn_offsets(am, ap, q, qp, tid_now() & 3);
            wg_fence();
            issue_qk(am, ap, q, qp, kd0);
            wg_commit();
            wg_wait<1>();
            pin(o);
            badmask |= ((attn_finish(o, head, quarter, it) | big) ? 1u : 0u) << it;
            big = bignext;
            wg_wait<0>();
            pin(am); pin(ap);
        }
        wo_release(sb, cs, 3);
    }
    {
        uint32_t unsafe;
        asm volatile("ld.shared.u32 %0, [%1];" : "=r"(unsafe) : "r"(sb + S_CNT + 16));
        if (unsafe) badmask = 15;
    }
    if (__syncthreads_or(badmask != 0)) {
        const int tid = tid_now(), wg = tid >> 7, c = tid & 3, rloc = ((tid >> 5) & 3) * 16 + ((tid & 31) >> 2);
        if (badmask) asm volatile("red.shared.or.b32 [%0], %1;" ::"r"(sb + S_CNT + 20 + 4 * wg), "r"(badmask) : "memory");
        __syncthreads();
        asm volatile("ld.shared.u32 %0, [%1];" : "=r"(badmask) : "r"(sb + S_CNT + 20 + 4 * wg));
        for (int i = 0; i < 4; i++) mbar_wait(sb + B_WB + 8 * i, 0);
        __syncthreads();
        if (tid == 0) {
            fence_async_smem();
            attn_issue_q(sb, head, quarter); attn_issue_kv(sb, head, 0, 9);
        }
        mbar_wait(sb + B_AQ, 1);
        for (int g = 0; g < 9; g++) mbar_wait(sb + B_AT + 8 * g, 1);
        for (int e = tid; e < S_ * 20; e += 256) {
            const int tok = e / 20, j = e % 20, grp = (tok >> 3) & 15;
            if (!((poly_mask() >> grp) & 1)) continue;
            const int d = (head & 1) ? (j + 4) % 20 : j;
            float a = 0;
            for (int k = 0; k < D_; k++) a = fmaf(__bfloat162float(g_xn[tok * D_ + k]), __bfloat162float(wqkv[(size_t)k * (3 * D_) + D_ + head * 20 + d]), a);
            const uint32_t addr = sb + AK + (tok >> 7) * 6144 + (j >> 3) * 2048 + (j & 7) * 2 + k_row_off(tok & 127);
            asm volatile("st.shared.b16 [%0], %1;" ::"r"(addr), "h"(__bfloat16_as_ushort(__float2bfloat16_rn(a))) : "memory");
        }
        fence_async_smem();
        __syncthreads();
        for (int it = 0; it < 4; it++) {
            if (!((badmask >> it) & 1)) continue;
            const int qt = wg + 2 * it;
            attn_tile_exact(q_addr(sb, it), sb + QZERO, kd0, vd0, 1.f, head, quarter * 512 + qt * 64 + rloc, c);
        }
        __syncthreads();
        if (tid == 0) {
            fence_async_smem();
            for (int i = 0; i < 4; i++) wo_issue_b(sb, cs, i);
        }
        wpar = 1;
    }
    if ((threadIdx.x & 127) == 0) {
        asm volatile("fence.release.gpu;" ::: "memory");
#pragma unroll
        for (int it = 0; it < 4; it++)
            asm volatile("red.relaxed.gpu.global.add.u32 [%0], 1;" ::"l"(g_sync + (C_O + quarter * 8 + (threadIdx.x >> 7) + 2 * it) * 32) : "memory");
    }
}

constexpr int MR = 30720, MNS = 6, M_SM = MNS * MR, M_BAR = M_SM + 32768;
template <int NROWS>
__device__ __forceinline__ void moe_rows(uint32_t a, int stride, const float* x0, const float* x1, float (&a0)[8], float (&a1)[8]) {
    uint4 v[NROWS];
    float4 p[NROWS / 4], q[NROWS / 4];
#pragma unroll
    for (int u = 0; u < NROWS; u++) v[u] = lds128(a + u * stride);
#pragma unroll
    for (int u = 0; u < NROWS / 4; u++) { p[u] = reinterpret_cast<const float4*>(x0)[u]; q[u] = reinterpret_cast<const float4*>(x1)[u]; }
#pragma unroll
    for (int u = 0; u < NROWS; u++) {
        const float xa = (u & 3) == 0 ? p[u / 4].x : ((u & 3) == 1 ? p[u / 4].y : ((u & 3) == 2 ? p[u / 4].z : p[u / 4].w));
        const float xb = (u & 3) == 0 ? q[u / 4].x : ((u & 3) == 1 ? q[u / 4].y : ((u & 3) == 2 ? q[u / 4].z : q[u / 4].w));
        const uint32_t e[4] = {v[u].x, v[u].y, v[u].z, v[u].w};
#pragma unroll
        for (int j = 0; j < 4; j++) {
            const float lo = bf_lo(e[j]), hi = bf_hi(e[j]);
            a0[2 * j] = fmaf(xa, lo, a0[2 * j]); a0[2 * j + 1] = fmaf(xa, hi, a0[2 * j + 1]);
            a1[2 * j] = fmaf(xb, lo, a1[2 * j]); a1[2 * j + 1] = fmaf(xb, hi, a1[2 * j + 1]);
        }
    }
}
__device__ __forceinline__ void moe_phase(uint8_t* smem, uint32_t sb, int part, const __nv_bfloat16* __restrict__ wg_, const __nv_bfloat16* __restrict__ wu_,
                                          const __nv_bfloat16* __restrict__ wd_) {
    float* xs = reinterpret_cast<float*>(smem + M_SM);
    float* hs = xs + 2 * D_;
    float* red2 = hs + 2 * 432;
    float* s_val = red2 + 6 * D_;
    int* s_ix = reinterpret_cast<int*>(s_val + 16);
    int* s_sel = s_ix + 16;
    const int tid = threadIdx.x, lane = tid & 31, warp = tid >> 5;
    const uint32_t full = sb + M_BAR, empty = full + 8 * MNS;
    if (tid == 0) {
        for (int s = 0; s < MNS; s++) { mbar_init(full + 8 * s, 1); mbar_init(empty + 8 * s, 7); }
        fence_mbar_init();
        fence_async_smem();
    }
    __syncthreads();
    if (warp == 7) {
        if (lane == 0) {
#pragma unroll 1
            for (int c = 0; c < 58; c++) {
                const int s = c % MNS;
                if (c >= MNS) mbar_wait(empty + 8 * s, (c / MNS - 1) & 1);
                const uint8_t* src = c < 40 ? reinterpret_cast<const uint8_t*>(c < 20 ? wg_ : wu_) + ((size_t)part * 160 + (c % 20) * 8) * (F_ * 2)
                                            : reinterpret_cast<const uint8_t*>(wd_) + ((size_t)part * 432 + (c - 40) * 24) * (D_ * 2);
                const uint32_t bytes = c < 40 ? 8 * F_ * 2 : 24 * D_ * 2;
                mbar_expect(full + 8 * s, bytes);
                bulk_g2s(sb + s * MR, src, bytes, full + 8 * s);
            }
        }
        __syncwarp();
        return;
    }
    if (tid < 16) await(C_LN + tid, 8);
    if (tid == 16) await(C_AUX, 128);
    asm volatile("barrier.sync 3, 224;" ::: "memory");
    unsigned long long best = 0, second = 0;
    float rv[10];
#pragma unroll
    for (int j = 0; j < 10; j++) rv[j] = __ldcg(&g_r[min(tid + 224 * j, S_ - 1)]);
#pragma unroll
    for (int j = 0; j < 10; j++) {
        const int i = tid + 224 * j;
        const uint32_t b = __float_as_uint(rv[j]);
        const unsigned long long key = i < S_ ? ((unsigned long long)((b >> 31) ? ~b : (b | 0x80000000u)) << 32) | (uint32_t)(~i) : 0ull;
        if (key > best) { second = best; best = key; } else if (key > second) second = key;
    }
#pragma unroll 1
    for (int o = 16; o; o >>= 1) {
        const unsigned long long pb = __shfl_xor_sync(0xffffffffu, best, o), ps = __shfl_xor_sync(0xffffffffu, second, o);
        const unsigned long long hi = best > pb ? best : pb, lo = best > pb ? pb : best, s2 = second > ps ? second : ps;
        best = hi; second = lo > s2 ? lo : s2;
    }
    unsigned long long* s_key = reinterpret_cast<unsigned long long*>(s_val);
    if (lane == 0) { s_key[warp] = best; s_key[8 + warp] = second; }
    asm volatile("barrier.sync 3, 224;" ::: "memory");
    if (tid == 0) {
        best = 0; second = 0;
        for (int w = 0; w < 7; w++)
            for (int h = 0; h < 2; h++) { const unsigned long long key = s_key[8 * h + w]; if (key > best) { second = best; best = key; } else if (key > second) second = key; }
        const int i0 = ~(uint32_t)best, i1 = ~(uint32_t)second;
        s_sel[0] = i0; s_sel[1] = i1;
        if (part == 0) {
            g_idx[0] = i0; g_idx[1] = i1;
            const uint32_t k0 = best >> 32, k1 = second >> 32;
            const float r0 = __uint_as_float((k0 >> 31) ? (k0 & 0x7FFFFFFFu) : ~k0), r1 = __uint_as_float((k1 >> 31) ? (k1 & 0x7FFFFFFFu) : ~k1);
            g_gate[0] = bfr(1.f / (1.f + __expf(-r0))); g_gate[1] = bfr(1.f / (1.f + __expf(-r1)));
        }
    }
    asm volatile("barrier.sync 3, 224;" ::: "memory");
    for (int i = tid; i < 2 * 160; i += 224) xs[i] = __bfloat162float(__ldcg(reinterpret_cast<const __nv_bfloat16*>(g_xn) + s_sel[i / 160] * D_ + part * 160 + i % 160));
    asm volatile("barrier.sync 3, 224;" ::: "memory");
#pragma unroll 1
    for (int mat = 0; mat < 2; mat++) {
        float a0[8], a1[8];
#pragma unroll
        for (int j = 0; j < 8; j++) { a0[j] = 0; a1[j] = 0; }
#pragma unroll 1
        for (int c = 0; c < 20; c++) {
            const int cc = mat * 20 + c, s = cc % MNS;
            mbar_wait(full + 8 * s, (cc / MNS) & 1);
            if (tid < 216) moe_rows<8>(sb + s * MR + tid * 16, F_ * 2, xs + c * 8, xs + 160 + c * 8, a0, a1);
            __syncwarp();
            if (lane == 0) mbar_arrive(empty + 8 * s);
        }
        if (tid < 216) {
            float* dst = g_part + ((part * 2 + mat) * 2) * F_ + tid * 8;
            *reinterpret_cast<float4*>(dst) = make_float4(a0[0], a0[1], a0[2], a0[3]); *reinterpret_cast<float4*>(dst + 4) = make_float4(a0[4], a0[5], a0[6], a0[7]);
            *reinterpret_cast<float4*>(dst + F_) = make_float4(a1[0], a1[1], a1[2], a1[3]); *reinterpret_cast<float4*>(dst + F_ + 4) = make_float4(a1[4], a1[5], a1[6], a1[7]);
        }
    }
    asm volatile("barrier.sync 3, 224;" ::: "memory");
    if (tid == 0) { signal(C_MOE1); await(C_MOE1, 4); }
    asm volatile("barrier.sync 3, 224;" ::: "memory");
    for (int i = tid; i < 2 * 432; i += 224) {
        const int tok = i / 432, n = part * 432 + i % 432;
        float g = 0, u = 0;
#pragma unroll
        for (int p = 0; p < 4; p++) { g += __ldcg(&g_part[((p * 2 + 0) * 2 + tok) * F_ + n]); u += __ldcg(&g_part[((p * 2 + 1) * 2 + tok) * F_ + n]); }
        g = bfr(g); u = bfr(u);
        const float sg = bfr(g / (1.f + __expf(-g)));
        hs[i] = bfr(sg * u);
    }
    asm volatile("barrier.sync 3, 224;" ::: "memory");
    {
        const int cg = tid % 80, kg = tid / 80;
        float a0[8], a1[8];
#pragma unroll
        for (int j = 0; j < 8; j++) { a0[j] = 0; a1[j] = 0; }
#pragma unroll 1
        for (int c = 0; c < 18; c++) {
            const int cc = 40 + c, s = cc % MNS;
            mbar_wait(full + 8 * s, (cc / MNS) & 1);
            if (tid < 160) moe_rows<12>(sb + s * MR + kg * 12 * (D_ * 2) + cg * 16, D_ * 2, hs + c * 24 + kg * 12, hs + 432 + c * 24 + kg * 12, a0, a1);
            __syncwarp();
            if (lane == 0) mbar_arrive(empty + 8 * s);
        }
        if (tid < 160) {
#pragma unroll
            for (int j = 0; j < 8; j++) { red2[(kg * 2 + 0) * D_ + cg * 8 + j] = a0[j]; red2[(kg * 2 + 1) * D_ + cg * 8 + j] = a1[j]; }
        }
    }
    asm volatile("barrier.sync 3, 224;" ::: "memory");
    for (int i = tid; i < 2 * D_; i += 224) g_y[part * 2 * D_ + i] = red2[i] + red2[2 * D_ + i];
    asm volatile("barrier.sync 3, 224;" ::: "memory");
    if (tid == 0) signal(C_MOE);
}

__host__ __device__ constexpr int wo_kb(int i) { return (i >> 1) + 5 * (i & 1); }
__host__ __device__ constexpr uint32_t wo_a_slot(int i) {
    return i < 3 ? WA + 8192 * i : (i < 5 ? 184320 + 8192 * (i - 3) : (i < 7 ? 102400 + 8192 * (i - 5) : WA + 8192 * (i - 7)));
}
__host__ __device__ constexpr uint32_t wo_b_slot(int i) { return i == 9 ? 0 : wo_kb(i) * 20480; }
__device__ __forceinline__ void wo_issue_a(uint32_t sb, const CUtensorMap* tmA, int rb, int i) {
    mbar_expect(sb + B_WF + 8 * i, 8192);
    tma2d(sb + wo_a_slot(i), tmA, wo_kb(i) * 64, rb * 64, sb + B_WF + 8 * i);
}
template <int I> __device__ __forceinline__ void wo_mma(float (&acc)[40], uint64_t da0, uint64_t db0) {
#pragma unroll
    for (int k = 0; k < 4; k++) MmaSS<80, 1>::go(acc, da0 + (wo_a_slot(I) >> 4) + 2 * k, db0 + (wo_b_slot(I) >> 4) + 320 * k, 1);
}
__device__ __forceinline__ void wo_phase(uint32_t sb, const CUtensorMap* tmA, const CUtensorMap* tmOut, int rb, int cs,
                                         const __nv_bfloat16* __restrict__ x, uint32_t wpar) {
    constexpr int N = 80;
    const int tid = threadIdx.x, lane = tid & 31, wg = tid >> 7;
    const int row = rb * 64 + ((tid >> 5) & 3) * 16 + (lane >> 2), col = cs * 160 + wg * 80 + 2 * (lane & 3);
    if ((tid & 127) == 0) {
        await(C_O + rb, 32);
        fence_async_global();
        if (wg == 0) { for (int i = 0; i < 3; i++) wo_issue_a(sb, tmA, rb, i); }
        else { wo_issue_a(sb, tmA, rb, 3); wo_issue_a(sb, tmA, rb, 4); }
    }
    uint32_t xv[2][N / 8], nv[2][N / 8];
#pragma unroll
    for (int h = 0; h < 2; h++)
#pragma unroll
        for (int j = 0; j < N / 8; j++) {
            xv[h][j] = __ldg(reinterpret_cast<const uint32_t*>(x + (size_t)(row + 8 * h) * D_ + col + 8 * j));
            nv[h][j] = __ldcg(reinterpret_cast<const uint32_t*>(g_xn + (size_t)(row + 8 * h) * D_ + col + 8 * j));
        }
    float acc[N / 2];
#pragma unroll
    for (int i = 0; i < N / 2; i++) acc[i] = 0.f;
    pin(acc);
    const uint64_t da0 = make_desc(sb, 16, 1024, 1), db0 = make_desc(sb + WB + (wg ? 1280 : 0), 2560, 128, 0);
    const uint32_t wf = sb + B_WF;
    mbar_wait(sb + B_WB, wpar); mbar_wait(sb + B_WB + 8, wpar); mbar_wait(wf, 0); mbar_wait(wf + 8, 0);
    wg_fence();
    wo_mma<0>(acc, da0, db0); wo_mma<1>(acc, da0, db0);
    wg_commit();
    mbar_wait(wf + 16, 0);
    wg_fence();
    wo_mma<2>(acc, da0, db0);
    wg_commit();
    wg_wait<1>();
    if ((tid & 127) == 0) {
        mbar_arrive(sb + B_WE);
        mbar_wait(sb + B_WE, 0);
        if (wg == 0) {
            mbar_expect(sb + B_WF + 80, 20480);
            bulk_g2s(sb + wo_b_slot(9), g_wo + cs * 204800 + 9 * 20480, 20480, sb + B_WF + 80);
            wo_issue_a(sb, tmA, rb, 5);
        } else { wo_issue_a(sb, tmA, rb, 6); wo_issue_a(sb, tmA, rb, 7); }
    }
    mbar_wait(sb + B_WB + 16, wpar); mbar_wait(wf + 24, 0); mbar_wait(wf + 32, 0);
    wg_fence();
    wo_mma<3>(acc, da0, db0); wo_mma<4>(acc, da0, db0);
    wg_commit();
    wg_wait<1>();
    if ((tid & 127) == 0) {
        mbar_arrive(sb + B_WE + 8);
        mbar_wait(sb + B_WE + 8, 0);
        wo_issue_a(sb, tmA, rb, 8 + wg);
    }
    mbar_wait(wf + 40, 0);
    wg_fence();
    wo_mma<5>(acc, da0, db0);
    mbar_wait(sb + B_WB + 24, wpar); mbar_wait(wf + 48, 0); mbar_wait(wf + 56, 0);
    wg_fence();
    wo_mma<6>(acc, da0, db0); wo_mma<7>(acc, da0, db0);
    mbar_wait(wf + 64, 0); mbar_wait(wf + 72, 0); mbar_wait(wf + 80, 0);
    wg_fence();
    wo_mma<8>(acc, da0, db0); wo_mma<9>(acc, da0, db0);
    wg_commit();
    if ((tid & 127) == 0) await(C_MOE, 4);
    wg_bar(tid >> 7);
    const int i0 = __ldcg(&g_idx[0]), i1 = __ldcg(&g_idx[1]);
    wg_wait<0>();
    pin(acc);
#pragma unroll
    for (int h = 0; h < 2; h++) {
        const int r = row + 8 * h;
        const int sel = r == i0 ? 0 : (r == i1 ? 1 : -1);
        if (sel >= 0) {
            const float gate = __ldcg(&g_gate[sel]);
#pragma unroll
            for (int j = 0; j < N / 8; j++) {
                const int cc = col + 8 * j;
                float y0 = 0, y1 = 0;
#pragma unroll
                for (int p = 0; p < 4; p++) { y0 += __ldcg(&g_y[(p * 2 + sel) * D_ + cc]); y1 += __ldcg(&g_y[(p * 2 + sel) * D_ + cc + 1]); }
                nv[h][j] = add_bf2(nv[h][j], pack_bf(bfr(y0) * gate, bfr(y1) * gate));
            }
        }
#pragma unroll
        for (int j = 0; j < N / 8; j++) {
            const uint32_t a = pack_bf(acc[4 * j + 2 * h], acc[4 * j + 2 * h + 1]);
            xv[h][j] = add_bf2(add_bf2(xv[h][j], a), nv[h][j]);
        }
    }
    {
        __syncthreads();
        const uint32_t stg = sb + WA;
        const int tr = ((tid >> 5) & 3) * 16 + ((lane >> 3) & 1) * 8 + (lane & 7);
        const uint32_t sa = stg + tr * 320 + wg * 160 + (lane >> 4) * 16;
#pragma unroll
        for (int j = 0; j < N / 8; j += 2) stsm4(sa + j * 16, xv[0][j], xv[1][j], xv[0][j + 1], xv[1][j + 1]);
        fence_async_smem();
        __syncthreads();
        if (tid == 0) {
            asm volatile("cp.async.bulk.tensor.2d.global.shared::cta.bulk_group [%0, {%2, %3}], [%1];"
                         ::"l"(tmOut), "r"(stg), "r"(cs * 160), "r"(rb * 64) : "memory");
            bulk_commit();
            asm volatile("cp.async.bulk.wait_group.read 0;" ::: "memory");
        }
    }
}

__global__ void __launch_bounds__(256, 1)
k_fused(const __grid_constant__ CUtensorMap tmXn, const __grid_constant__ CUtensorMap tmWqkv, const __grid_constant__ CUtensorMap tmO,
        const __grid_constant__ CUtensorMap tmOut, const __nv_bfloat16* __restrict__ wo, const __nv_bfloat16* __restrict__ x, const __nv_bfloat16* __restrict__ wqkv,
        const __nv_bfloat16* __restrict__ wr, const __nv_bfloat16* __restrict__ wgate, const __nv_bfloat16* __restrict__ wup,
        const __nv_bfloat16* __restrict__ wdown) {
    extern __shared__ __align__(1024) uint8_t smem[];
    const uint32_t sb = (smem_u32(smem) + 1023) & ~1023u;
    const int tid = threadIdx.x, cta = blockIdx.x;
    if (cta < 128) {
        const int mb = cta >> 3, nb = cta & 7;
        const int row = cta * 16 + (tid >> 4), l16 = tid & 15;
#pragma unroll
        for (int i = 0; i < 5; i++) cp_async16(sb + LNX + (tid >> 4) * 1280 + (l16 + 16 * i) * 16, reinterpret_cast<const uint4*>(x + (size_t)row * D_) + l16 + 16 * i);
        if (tid < 80) cp_async16(sb + LNX + 16 * 1280 + tid * 16, reinterpret_cast<const uint4*>(wr) + tid);
        uint4 wv[2];
        uint32_t wdst[2];
#pragma unroll
        for (int i = 0; i < 2; i++) {
            const int blk = min(cta * 8 + (tid >> 5) + 1024 * i, 1599), cs = blk / 400, kg = (blk % 400) / 5, nc = (blk % 5) * 4 + ((tid >> 3) & 3);
            wv[i] = __ldg(reinterpret_cast<const uint4*>(wo + (size_t)(kg * 8 + (tid & 7)) * D_ + cs * 160 + nc * 8));
            wdst[i] = cs * 204800 + kg * 2560 + nc * 128 + (tid & 7) * 16;
        }
        if (tid == 0) {
            for (int s = 0; s < 4; s++) { mbar_init(sb + B_GF + 8 * s, 1); mbar_init(sb + B_GE + 8 * s, 2); }
            fence_mbar_init();
            fence_async_smem();
            prefetch_tmap(&tmWqkv);
            for (int kb = 0; kb < QB0; kb++) qkv_issue_b(sb, &tmWqkv, kb, nb);
        }
        if (tid == 32) {
            for (int i = 0; i < 10; i++) mbar_init(sb + B_AT + 8 * i, 1);
            for (int i = 0; i < 15; i++) mbar_init(sb + B_WB + 8 * i, 1);
            for (int i = 0; i < 2; i++) mbar_init(sb + B_WE + 8 * i, 2);
            for (int i = 0; i < 7; i++) asm volatile("st.shared.u32 [%0], 0;" ::"r"(sb + S_CNT + 4 * i) : "memory");
            fence_mbar_init();
            fence_async_smem();
            prefetch_tmap(&tmXn); prefetch_tmap(&tmO); prefetch_tmap(&tmOut);
        }
        asm volatile("cp.async.wait_all;" ::: "memory");
        __syncthreads();
        *reinterpret_cast<uint4*>(g_wo + wdst[0]) = wv[0];
        *reinterpret_cast<uint4*>(g_wo + wdst[1]) = wv[1];
        ln_phase(sb, row, l16);
        __syncthreads();
        if (tid == 0) {
            bulk_s2g(g_xn + (size_t)cta * 16 * D_, sb + LNX, 16 * D_ * 2);
            bulk_commit();
        }
        ln_score(sb, row, l16);
        __syncwarp();
        if (tid == 0) {
            bulk_wait0();
            fence_async_global();
            signal(C_LN + mb);
            await(C_LN + mb, 8);
            fence_async_global();
            for (int kb = 0; kb < 4; kb++) {
                if (kb >= QB0) qkv_issue_b(sb, &tmWqkv, kb, nb);
                qkv_issue_a(sb, &tmXn, kb, mb);
            }
        }
        if (tid >= 32) {
            asm volatile("barrier.sync 4, 224;" ::: "memory");
            if (tid == 32) {
                asm volatile("cp.async.bulk.prefetch.L2.global [%0], 17280;" ::"l"(reinterpret_cast<const uint8_t*>(wgate) + cta * 17280) : "memory");
                asm volatile("cp.async.bulk.prefetch.L2.global [%0], 17280;" ::"l"(reinterpret_cast<const uint8_t*>(wup) + cta * 17280) : "memory");
                asm volatile("cp.async.bulk.prefetch.L2.global [%0], 17280;" ::"l"(reinterpret_cast<const uint8_t*>(wdown) + cta * 17280) : "memory");
                signal(C_AUX);
            }
        }
        qkv_phase(sb, &tmXn, &tmWqkv, mb, nb);
        uint32_t wpar = 0;
        attn_phase(sb, cta >> 2, cta & 3, cta & 3, wqkv, wpar);
        wo_phase(sb, &tmO, &tmOut, cta >> 2, cta & 3, x, wpar);
    } else {
        moe_phase(smem + (sb - smem_u32(smem)), sb, cta - 128, wgate, wup, wdown);
    }
    __syncthreads();
    if (tid == 0) {
        if (atomicAdd(&g_sync[C_EXIT * 32], 1u) == gridDim.x - 1) {
            for (int i = 0; i < C_NUM; i++) g_sync[i * 32] = 0;
        }
    }
}

}

typedef CUresult (*EncodeFn)(CUtensorMap*, CUtensorMapDataType, cuuint32_t, void*, const cuuint64_t*, const cuuint64_t*, const cuuint32_t*, const cuuint32_t*,
                             CUtensorMapInterleave, CUtensorMapSwizzle, CUtensorMapL2promotion, CUtensorMapFloatOOBfill);

static void encode2d(EncodeFn fn, CUtensorMap* tm, const void* base, uint64_t cols, uint64_t rows, uint32_t bc, uint32_t br, CUtensorMapSwizzle sw) {
    cuuint64_t dims[2] = {cols, rows};
    cuuint64_t strides[1] = {cols * 2};
    cuuint32_t box[2] = {bc, br}, es[2] = {1, 1};
    fn(tm, CU_TENSOR_MAP_DATA_TYPE_BFLOAT16, 2, const_cast<void*>(base), dims, strides, box, es, CU_TENSOR_MAP_INTERLEAVE_NONE, sw,
       CU_TENSOR_MAP_L2_PROMOTION_L2_256B, CU_TENSOR_MAP_FLOAT_OOB_FILL_NONE);
}

extern "C" void kernel_launch(void* const* d_in, const int* in_sizes, int n_in, void* d_out, int out_size) {
    const __nv_bfloat16* x = (const __nv_bfloat16*)d_in[0];
    const __nv_bfloat16* wqkv = (const __nv_bfloat16*)d_in[1];
    const __nv_bfloat16* wo = (const __nv_bfloat16*)d_in[2];
    const __nv_bfloat16* wr = (const __nv_bfloat16*)d_in[4];
    const __nv_bfloat16* wgate = (const __nv_bfloat16*)d_in[5];
    const __nv_bfloat16* wup = (const __nv_bfloat16*)d_in[6];
    const __nv_bfloat16* wdown = (const __nv_bfloat16*)d_in[7];
    __nv_bfloat16* out = (__nv_bfloat16*)d_out;

    static EncodeFn enc = nullptr;
    static void *p_xn = nullptr, *p_o = nullptr;
    if (!enc) {
        void* fn = nullptr;
        cudaDriverEntryPointQueryResult qr;
        cudaGetDriverEntryPoint("cuTensorMapEncodeTiled", &fn, cudaEnableDefault, &qr);
        enc = (EncodeFn)fn;
        cudaGetSymbolAddress(&p_xn, g_xn);
        cudaGetSymbolAddress(&p_o, g_o);
        cudaFuncSetAttribute(k_fused, cudaFuncAttributeMaxDynamicSharedMemorySize, SMEM_BYTES);
    }
    CUtensorMap tmXn, tmWqkv, tmO, tmOut;
    encode2d(enc, &tmXn, p_xn, D_, S_, 64, 128, CU_TENSOR_MAP_SWIZZLE_128B);
    encode2d(enc, &tmWqkv, wqkv, 3 * D_, D_, 64, 64, CU_TENSOR_MAP_SWIZZLE_128B);
    encode2d(enc, &tmO, p_o, D_, S_, 64, 64, CU_TENSOR_MAP_SWIZZLE_128B);
    encode2d(enc, &tmOut, out, D_, S_, 160, 64, CU_TENSOR_MAP_SWIZZLE_NONE);

    k_fused<<<132, 256, SMEM_BYTES, cudaStreamPerThread>>>(tmXn, tmWqkv, tmO, tmOut, wo, x, wqkv, wr, wgate, wup, wdown);
}
```
